```python
import torch

def _softmax(x, axis=-1):
    return torch.softmax(x, dim=axis)
def _gelu(x):
    return torch.nn.functional.gelu(x, approximate="tanh")
def _silu(x):
    return torch.nn.functional.silu(x)
def _sigmoid(x):
    return torch.sigmoid(x)
def _layernorm(x, axis=-1, eps=1e-5):
    m = x.mean(dim=axis, keepdim=True)
    v = x.var(dim=axis, keepdim=True, unbiased=False)
    return (x - m) / torch.sqrt(v + eps)
def _scatter_add(tgt, idx, src, axis=0):
    return tgt.clone().index_add_(axis, idx, src)
def _segment_sum(src, seg, n):
    out = torch.zeros((n,) + src.shape[1:], dtype=src.dtype)
    return out.index_add_(0, seg, src)
def _pad(x, pw):
    flat = tuple(v for pair in reversed(pw) for v in pair)
    return torch.nn.functional.pad(x, flat)

kernel_name = 'standalone__deep_cross_pnn__recsys'

def setup_inputs():

    _w = (lambda a: (lambda t: t.to(torch.bfloat16) if t.is_floating_point() else t)(torch.as_tensor(a)))
    B, F, D, V = 4096, 26, 128, min(100000, 100000)
    H = 4 * D
    return {
        "idx": _w((lambda lo, hi, *s: torch.randint(lo, hi, s))(0, V, B, F).to(torch.int64)),
        "table": _w((lambda *s: torch.randn(*s, dtype=torch.bfloat16) * 1.6)(V, D) * (D ** -0.5)),
        "w_p": _w((lambda *s: torch.randn(*s, dtype=torch.bfloat16) * 0.05)(F * F) * ((F * F) ** -0.5)),
        "w1": _w((lambda *s: torch.randn(*s, dtype=torch.bfloat16) * 1.6)(F * D, H) * ((F * D) ** -0.5)),
        "b1": _w((lambda *s: torch.randn(*s, dtype=torch.bfloat16) * 12.8)(H) * 0.01),
        "w2": _w((lambda *s: torch.randn(*s, dtype=torch.bfloat16) * 0.05)(H) * (H ** -0.5)),
        "b2": _w((lambda *s: torch.randn(*s, dtype=torch.bfloat16) * 12.8)(1) * 0.01),
    }

def reference(idx, table, w_p, w1, b1, w2, b2):
    emb = table[idx]
    B = emb.shape[0]; F = emb.shape[1]; D = emb.shape[2]
    ip = torch.einsum('bid,bjd->bij', emb, emb)
    ip = ip.reshape(B, F * F)
    logit_p = ip @ w_p
    z = emb.reshape(B, F * D)
    h = _gelu(z @ w1 + b1)
    logit_d = h @ w2 + b2
    return logit_p + logit_d
```

```cpp
#include <cuda_runtime.h>
#include <cuda.h>
#include <cuda_bf16.h>
#include <stdint.h>

namespace {

constexpr int kB = 4096, kF = 26, kD = 128, kH = 512;
constexpr int NST = 4;
constexpr int A_BYTES = 16384;
constexpr int B_BYTES = 32768;
constexpr int STAGE = A_BYTES + B_BYTES;
constexpr int NITER = 26;
constexpr int TAILN = 2;
constexpr int OFF_X = NST * STAGE;
constexpr int OFF_BAR = OFF_X + 32768;
constexpr int OFF_W2 = OFF_BAR + 128;
constexpr int OFF_CF = OFF_W2 + 1024;
constexpr int OFF_LP = OFF_CF + 1792;
constexpr int SMEM_BYTES = OFF_LP + 128;
constexpr int OFF_B1 = OFF_X + 16384;
constexpr int BAR_FULL = 0, BAR_EMPTY = 32, BAR_XFULL = 64, BAR_XREADY = 96, BAR_PNN = 104, BAR_IDX = 112, BAR_GO = 120;

__device__ unsigned long long g_lp[kB];
__device__ unsigned long long g_slots[kB];

__device__ __forceinline__ uint32_t smem_u32(const void* p) { return (uint32_t)__cvta_generic_to_shared(p); }
__device__ __forceinline__ void mbar_init(uint32_t bar, uint32_t cnt) { asm volatile("mbarrier.init.shared::cta.b64 [%0], %1;" ::"r"(bar), "r"(cnt) : "memory"); }
__device__ __forceinline__ void mbar_expect_tx(uint32_t bar, uint32_t bytes) { asm volatile("mbarrier.arrive.expect_tx.shared::cta.b64 _, [%0], %1;" ::"r"(bar), "r"(bytes) : "memory"); }
__device__ __forceinline__ void mbar_arrive(uint32_t bar) { asm volatile("mbarrier.arrive.shared::cta.b64 _, [%0];" ::"r"(bar) : "memory"); }
__device__ __forceinline__ bool mbar_try(uint32_t bar, uint32_t parity) {
  uint32_t ok;
  asm volatile("{\n.reg .pred p;\nmbarrier.try_wait.parity.shared::cta.b64 p, [%1], %2;\nselp.u32 %0, 1, 0, p;\n}" : "=r"(ok) : "r"(bar), "r"(parity) : "memory");
  return ok;
}
__device__ __forceinline__ void mbar_wait(uint32_t bar, uint32_t parity) {
  int n = 0;
  while (!mbar_try(bar, parity)) { if (++n > (1 << 20)) __trap(); }
}
__device__ __forceinline__ uint32_t mapa(uint32_t a, uint32_t cta) { uint32_t r; asm volatile("mapa.shared::cluster.u32 %0, %1, %2;" : "=r"(r) : "r"(a), "r"(cta)); return r; }
__device__ __forceinline__ void tma3d(uint32_t dst, const void* tmap, int c0, int c1, int c2, uint32_t bar) {
  asm volatile("cp.async.bulk.tensor.3d.shared::cluster.global.mbarrier::complete_tx::bytes [%0], [%1, {%3, %4, %5}], [%2];" ::"r"(dst), "l"(tmap), "r"(bar), "r"(c0), "r"(c1), "r"(c2) : "memory");
}
__device__ __forceinline__ void cp16_256(uint32_t dst, const void* src) { asm volatile("cp.async.cg.shared.global.L2::256B [%0], [%1], 16;" ::"r"(dst), "l"(src) : "memory"); }
__device__ __forceinline__ void cp16(uint32_t dst, const void* src) { asm volatile("cp.async.cg.shared.global [%0], [%1], 16;" ::"r"(dst), "l"(src) : "memory"); }
__device__ __forceinline__ void cp_arrive_noinc(uint32_t bar) { asm volatile("cp.async.mbarrier.arrive.noinc.shared::cta.b64 [%0];" ::"r"(bar) : "memory"); }
__device__ __forceinline__ void wg_fence() { asm volatile("wgmma.fence.sync.aligned;" ::: "memory"); }
__device__ __forceinline__ void wg_commit() { asm volatile("wgmma.commit_group.sync.aligned;" ::: "memory"); }
template <int N> __device__ __forceinline__ void wg_wait() { asm volatile("wgmma.wait_group.sync.aligned %0;" ::"n"(N) : "memory"); }
__device__ __forceinline__ void fence_async() { asm volatile("fence.proxy.async.shared::cta;" ::: "memory"); }
__device__ __forceinline__ uint64_t make_desc(uint32_t addr, uint32_t lbo, uint32_t sbo) {
  return (uint64_t)((addr & 0x3FFFF) >> 4) | ((uint64_t)(lbo >> 4) << 16) | ((uint64_t)(sbo >> 4) << 32) | ((uint64_t)1 << 62);
}
__device__ __forceinline__ float bf16lo(uint32_t v) { return __uint_as_float(v << 16); }
__device__ __forceinline__ float bf16hi(uint32_t v) { return __uint_as_float(v & 0xffff0000u); }
__device__ __forceinline__ uint32_t pack_bf16(float lo, float hi) { uint32_t r; asm("cvt.rn.bf16x2.f32 %0, %1, %2;" : "=r"(r) : "f"(hi), "f"(lo)); return r; }
__device__ __forceinline__ float ldbf(const __nv_bfloat16* p, int i) { return __bfloat162float(p[i]); }
__device__ __forceinline__ void mma16816(float (&c)[4], uint32_t a0, uint32_t a1, uint32_t a2, uint32_t a3, uint32_t b0, uint32_t b1) {
  asm volatile("mma.sync.aligned.m16n8k16.row.col.f32.bf16.bf16.f32 {%0,%1,%2,%3},{%4,%5,%6,%7},{%8,%9},{%0,%1,%2,%3};"
               : "+f"(c[0]), "+f"(c[1]), "+f"(c[2]), "+f"(c[3]) : "r"(a0), "r"(a1), "r"(a2), "r"(a3), "r"(b0), "r"(b1));
}
__device__ __forceinline__ void wgmma_n256(float (&d)[128], uint64_t descA, uint64_t descB) {
  asm volatile(
    "{\n.reg .pred p;\nsetp.eq.u32 p, 1, 1;\n"
    "wgmma.mma_async.sync.aligned.m64n256k16.f32.bf16.bf16 "
    "{%0, %1, %2, %3, %4, %5, %6, %7, %8, %9, %10, %11, %12, %13, %14, %15, %16, %17, %18, %19, %20, %21, %22, %23, %24, %25, %26, %27, %28, %29, %30, %31, %32, %33, %34, %35, %36, %37, %38, %39, %40, %41, %42, %43, %44, %45, %46, %47, %48, %49, %50, %51, %52, %53, %54, %55, %56, %57, %58, %59, %60, %61, %62, %63, %64, %65, %66, %67, %68, %69, %70, %71, %72, %73, %74, %75, %76, %77, %78, %79, %80, %81, %82, %83, %84, %85, %86, %87, %88, %89, %90, %91, %92, %93, %94, %95, %96, %97, %98, %99, %100, %101, %102, %103, %104, %105, %106, %107, %108, %109, %110, %111, %112, %113, %114, %115, %116, %117, %118, %119, %120, %121, %122, %123, %124, %125, %126, %127}, "
    "%128, %129, p, 1, 1, 0, 1;\n}\n"
    : "+f"(d[0]), "+f"(d[1]), "+f"(d[2]), "+f"(d[3]), "+f"(d[4]), "+f"(d[5]), "+f"(d[6]), "+f"(d[7]), "+f"(d[8]), "+f"(d[9]), "+f"(d[10]), "+f"(d[11]), "+f"(d[12]), "+f"(d[13]), "+f"(d[14]), "+f"(d[15]), "+f"(d[16]), "+f"(d[17]), "+f"(d[18]), "+f"(d[19]), "+f"(d[20]), "+f"(d[21]), "+f"(d[22]), "+f"(d[23]), "+f"(d[24]), "+f"(d[25]), "+f"(d[26]), "+f"(d[27]), "+f"(d[28]), "+f"(d[29]), "+f"(d[30]), "+f"(d[31]), "+f"(d[32]), "+f"(d[33]), "+f"(d[34]), "+f"(d[35]), "+f"(d[36]), "+f"(d[37]), "+f"(d[38]), "+f"(d[39]), "+f"(d[40]), "+f"(d[41]), "+f"(d[42]), "+f"(d[43]), "+f"(d[44]), "+f"(d[45]), "+f"(d[46]), "+f"(d[47]), "+f"(d[48]), "+f"(d[49]), "+f"(d[50]), "+f"(d[51]), "+f"(d[52]), "+f"(d[53]), "+f"(d[54]), "+f"(d[55]), "+f"(d[56]), "+f"(d[57]), "+f"(d[58]), "+f"(d[59]), "+f"(d[60]), "+f"(d[61]), "+f"(d[62]), "+f"(d[63]), "+f"(d[64]), "+f"(d[65]), "+f"(d[66]), "+f"(d[67]), "+f"(d[68]), "+f"(d[69]), "+f"(d[70]), "+f"(d[71]), "+f"(d[72]), "+f"(d[73]), "+f"(d[74]), "+f"(d[75]), "+f"(d[76]), "+f"(d[77]), "+f"(d[78]), "+f"(d[79]), "+f"(d[80]), "+f"(d[81]), "+f"(d[82]), "+f"(d[83]), "+f"(d[84]), "+f"(d[85]), "+f"(d[86]), "+f"(d[87]), "+f"(d[88]), "+f"(d[89]), "+f"(d[90]), "+f"(d[91]), "+f"(d[92]), "+f"(d[93]), "+f"(d[94]), "+f"(d[95]), "+f"(d[96]), "+f"(d[97]), "+f"(d[98]), "+f"(d[99]), "+f"(d[100]), "+f"(d[101]), "+f"(d[102]), "+f"(d[103]), "+f"(d[104]), "+f"(d[105]), "+f"(d[106]), "+f"(d[107]), "+f"(d[108]), "+f"(d[109]), "+f"(d[110]), "+f"(d[111]), "+f"(d[112]), "+f"(d[113]), "+f"(d[114]), "+f"(d[115]), "+f"(d[116]), "+f"(d[117]), "+f"(d[118]), "+f"(d[119]), "+f"(d[120]), "+f"(d[121]), "+f"(d[122]), "+f"(d[123]), "+f"(d[124]), "+f"(d[125]), "+f"(d[126]), "+f"(d[127])
    : "l"(descA), "l"(descB));
}
__device__ __forceinline__ float gelu_dot(float x, float w2h, float acc) {
  float x2 = x * x;
  float p = fmaf(x2, 0.035677408136300125f, 0.7978845608028654f);
  float u = x * p, t;
  asm("tanh.approx.f32 %0, %1;" : "=f"(t) : "f"(u));
  float y = fmaf(x, t, x);
  return fmaf(y, w2h, acc);
}

struct GeluOps { uint32_t p[16]; float w[16]; };
__device__ __forceinline__ void gelu_load(GeluOps& o, uint32_t xb, uint32_t w2a) {
#pragma unroll
  for (int i = 0; i < 4; i++)
    asm volatile("ld.shared.v4.b32 {%0,%1,%2,%3}, [%4];" : "=r"(o.p[4 * i]), "=r"(o.p[4 * i + 1]), "=r"(o.p[4 * i + 2]), "=r"(o.p[4 * i + 3]) : "r"(xb + i * 2048));
#pragma unroll
  for (int j = 0; j < 8; j++) asm volatile("ld.shared.v2.f32 {%0,%1}, [%2];" : "=f"(o.w[2 * j]), "=f"(o.w[2 * j + 1]) : "r"(w2a + j * 32));
}
template <int C>
__device__ __forceinline__ void gelu_chunk(const float (&x)[64], const GeluOps& o, float& s0, float& s1) {
#pragma unroll
  for (int j = 0; j < 8; j++) {
    s0 = gelu_dot(x[32 * C + 4 * j + 0] + bf16lo(o.p[2 * j]), o.w[2 * j], s0);
    s0 = gelu_dot(x[32 * C + 4 * j + 1] + bf16hi(o.p[2 * j]), o.w[2 * j + 1], s0);
    s1 = gelu_dot(x[32 * C + 4 * j + 2] + bf16lo(o.p[2 * j + 1]), o.w[2 * j], s1);
    s1 = gelu_dot(x[32 * C + 4 * j + 3] + bf16hi(o.p[2 * j + 1]), o.w[2 * j + 1], s1);
  }
}

template <int C>
__device__ __forceinline__ void send_chunk(float (&acc)[128], uint32_t rx, uint32_t rbar) {
#pragma unroll
  for (int i = 0; i < 4; i++) {
    const int b = 32 * C + 8 * i;
    uint32_t p0 = pack_bf16(acc[b + 0], acc[b + 1]), p1 = pack_bf16(acc[b + 2], acc[b + 3]);
    uint32_t p2 = pack_bf16(acc[b + 4], acc[b + 5]), p3 = pack_bf16(acc[b + 6], acc[b + 7]);
    asm volatile("st.async.weak.shared::cluster.mbarrier::complete_tx::bytes.v4.b32 [%0], {%1,%2,%3,%4}, [%5];"
                 ::"r"(rx + C * 8192 + i * 2048), "r"(p0), "r"(p1), "r"(p2), "r"(p3), "r"(rbar + C * 8) : "memory");
  }
}

__device__ __forceinline__ uint32_t lds32(uint32_t a) { uint32_t v; asm volatile("ld.shared.u32 %0, [%1];" : "=r"(v) : "r"(a)); return v; }
__device__ __forceinline__ void gram_step(float (&G)[5][4], uint32_t z, uint32_t e0l, uint32_t e0h, uint32_t e1l, uint32_t e1h,
                                          uint32_t e2l, uint32_t e2h, uint32_t e3l, uint32_t e3h) {
  uint32_t q0 = e0l ^ z, q2 = e0h ^ z, q1 = e1l ^ z, q3 = e1h ^ z;
  const uint32_t p0 = e1l | z, p1 = e2l | z, p2 = e1h | z, p3 = e2h | z;
  mma16816(G[0], q0, q1, q2, q3, e0l, e0h);
  mma16816(G[1], p0, p1, p2, p3, e1l, e1h);
  q1 = e2l ^ z; q3 = e2h ^ z;
  mma16816(G[2], q0, q1, q2, q3, e2l, e2h);
  mma16816(G[3], p0, p1, p2, p3, e3l, e3h);
  q1 = e3l ^ z; q3 = e3h ^ z;
  mma16816(G[4], q0, q1, q2, q3, e3l, e3h);
}

struct Chunk { uint4 e[4]; };
__device__ __forceinline__ void gram_chunk(float (&G)[5][4], uint32_t z, const Chunk& ch) {
  gram_step(G, z, ch.e[0].x, ch.e[0].y, ch.e[1].x, ch.e[1].y, ch.e[2].x, ch.e[2].y, ch.e[3].x, ch.e[3].y);
  gram_step(G, z, ch.e[0].z, ch.e[0].w, ch.e[1].z, ch.e[1].w, ch.e[2].z, ch.e[2].w, ch.e[3].z, ch.e[3].w);
}
struct Coef { float c[5][4]; };
__device__ __forceinline__ void load_coef(Coef& cf, uint32_t sb, int lane) {
#pragma unroll
  for (int t = 0; t < 5; t++) {
    const uint32_t a = (t < 3) ? sb + OFF_CF + t * 512 + lane * 16 : sb + OFF_CF + 1536 + (t - 3) * 128 + (lane >> 2) * 16;
    asm volatile("ld.shared.v4.f32 {%0,%1,%2,%3}, [%4];" : "=f"(cf.c[t][0]), "=f"(cf.c[t][1]), "=f"(cf.c[t][2]), "=f"(cf.c[t][3]) : "r"(a));
    if (t >= 3 && (lane & 3) != 0) cf.c[t][0] = cf.c[t][1] = cf.c[t][2] = cf.c[t][3] = 0.f;
  }
}
__device__ __forceinline__ void load_sample(Chunk (&ch)[4], uint32_t base, uint32_t sw, bool g3) {
#pragma unroll
  for (int c = 0; c < 4; c++) {
#pragma unroll
    for (int t = 0; t < 3; t++)
      asm volatile("ld.shared.v4.u32 {%0,%1,%2,%3}, [%4];" : "=r"(ch[c].e[t].x), "=r"(ch[c].e[t].y), "=r"(ch[c].e[t].z), "=r"(ch[c].e[t].w) : "r"(base + t * 2048 + ((c * 64) ^ sw)));
    ch[c].e[3] = make_uint4(0, 0, 0, 0);
    if (g3) asm volatile("ld.shared.v4.u32 {%0,%1,%2,%3}, [%4];" : "=r"(ch[c].e[3].x), "=r"(ch[c].e[3].y), "=r"(ch[c].e[3].z), "=r"(ch[c].e[3].w) : "r"(base + 3 * 2048 + ((c * 64) ^ sw)));
  }
}
__device__ __forceinline__ void load_chunk_s(Chunk& ch, uint32_t base, uint32_t sw, bool g3, int c) {
#pragma unroll
  for (int t = 0; t < 3; t++)
    asm volatile("ld.shared.v4.u32 {%0,%1,%2,%3}, [%4];" : "=r"(ch.e[t].x), "=r"(ch.e[t].y), "=r"(ch.e[t].z), "=r"(ch.e[t].w) : "r"(base + t * 2048 + ((c * 64) ^ sw)));
  if (g3) asm volatile("ld.shared.v4.u32 {%0,%1,%2,%3}, [%4];" : "=r"(ch.e[3].x), "=r"(ch.e[3].y), "=r"(ch.e[3].z), "=r"(ch.e[3].w) : "r"(base + 3 * 2048 + ((c * 64) ^ sw)));
}
__device__ __forceinline__ float gram_sample(const Chunk (&ch)[4], uint32_t z, const Coef& cf) {
  float G[5][4];
#pragma unroll
  for (int t = 0; t < 5; t++) { G[t][0] = G[t][1] = G[t][2] = G[t][3] = 0.f; }
#pragma unroll
  for (int c = 0; c < 4; c++) gram_chunk(G, z, ch[c]);
  float lp = 0.f;
#pragma unroll
  for (int t = 0; t < 5; t++) lp += fmaf(G[t][0], cf.c[t][0], fmaf(G[t][1], cf.c[t][1], fmaf(G[t][2], cf.c[t][2], G[t][3] * cf.c[t][3])));
  return lp;
}

constexpr int PNN_LOCAL = 27;
__device__ __forceinline__ uint32_t pnn_base(uint32_t sb, uint32_t pp, int g, int q) {
  const int v = pp / 7, R0 = (pp - 7 * v) * kF;
  return sb + ((v + 2) & 3) * STAGE + (R0 + g) * 256 + q * 16;
}
__device__ __forceinline__ uint32_t pnn_full(uint32_t sb, uint32_t pp) { return sb + OFF_BAR + BAR_FULL + 8 * ((pp / 7 + 2) & 3); }
__device__ __forceinline__ uint32_t pnn_par(uint32_t pp) { return ((26 + pp / 7) >> 2) & 1; }
__device__ __forceinline__ float pnn_one(uint32_t sb, uint32_t pp, int lane, uint32_t z, bool wait_go) {
  const int g = lane >> 2, q = lane & 3;
  Chunk ch[4];
#pragma unroll
  for (int c = 0; c < 4; c++) ch[c].e[3] = make_uint4(0, 0, 0, 0);
  mbar_wait(pnn_full(sb, pp), pnn_par(pp));
  __syncwarp();
#pragma unroll
  for (int c = 0; c < 4; c++) load_chunk_s(ch[c], pnn_base(sb, pp, g, q), (g & 1) << 6, g < 2, c);
  if (wait_go) { mbar_wait(sb + OFF_BAR + BAR_GO, 0); __syncwarp(); }
  float G[5][4];
#pragma unroll
  for (int t = 0; t < 5; t++) { G[t][0] = G[t][1] = G[t][2] = G[t][3] = 0.f; }
  Coef cf;
#pragma unroll
  for (int c = 0; c < 4; c++) {
    gram_chunk(G, z, ch[c]);
    if (c == 2) load_coef(cf, sb, lane);
  }
  float lp = 0.f;
#pragma unroll
  for (int t = 0; t < 5; t++) lp += fmaf(G[t][0], cf.c[t][0], fmaf(G[t][1], cf.c[t][1], fmaf(G[t][2], cf.c[t][2], G[t][3] * cf.c[t][3])));
  return lp;
}
template <int N>
__device__ __forceinline__ void pnn_publish(float (&lp)[N], const int (&p)[N], uint32_t sb, int lane) {
#pragma unroll
  for (int o = 16; o > 0; o >>= 1) {
#pragma unroll
    for (int i = 0; i < N; i++) lp[i] += __shfl_xor_sync(0xffffffffu, lp[i], o);
  }
#pragma unroll
  for (int i = 0; i < N; i++)
    if (lane == i && p[i] >= 0) asm volatile("st.shared.f32 [%0], %1;" ::"r"(sb + OFF_LP + p[i] * 4), "f"(lp[i]) : "memory");
  __syncwarp();
  if (lane == 0) mbar_arrive(sb + OFF_BAR + BAR_PNN);
}

__device__ __forceinline__ void build_coef(const __nv_bfloat16* __restrict__ w_p, uint32_t sb, int tid) {
  if (tid < 112) {
    const int t = (tid < 96) ? (tid >> 5) : 3 + ((tid - 96) >> 3);
    const int g = (tid < 96) ? ((tid & 31) >> 2) : (tid & 7), q = (tid < 96) ? (tid & 3) : 0;
    const int X = (t == 1 || t == 3) ? 1 : 0, Y = (t == 0) ? 1 : (t == 4 ? 3 : 2), Z = (t < 3) ? t : 3;
    float v[4];
#pragma unroll
    for (int e = 0; e < 4; e++) {
      const int G = (e < 2) ? X : Y;
      const int i = 8 * G + g, j = 8 * Z + 2 * q + (e & 1);
      const bool ok = (i < kF) && (j < kF);
      const float a = ok ? ldbf(w_p, i * kF + j) : 0.f;
      const float b = (ok && G != Z) ? ldbf(w_p, j * kF + i) : 0.f;
      v[e] = a + b;
    }
    asm volatile("st.shared.v4.f32 [%0], {%1,%2,%3,%4};" ::"r"(sb + OFF_CF + tid * 16), "f"(v[0]), "f"(v[1]), "f"(v[2]), "f"(v[3]) : "memory");
  }
}

constexpr int SP_N = 160, SP_BUF = 26 * 256, SP_IDX = 12 * 2 * SP_BUF;
__device__ __noinline__ void pnn_spare(const int* __restrict__ idx, const __nv_bfloat16* __restrict__ table, const __nv_bfloat16* __restrict__ w_p, uint32_t sb, int tid, int j) {
  const int warp = tid >> 5, lane = tid & 31, g = lane >> 2, q = lane & 3;
  auto gsof = [&](int u) { const int bq = u / 5, b = 32 * j + bq; return (b >> 2) * 128 + 64 * (b & 1) + 32 * ((b >> 1) & 1) + 27 + (u - 5 * bq); };
  for (int e = tid; e < SP_N * kF; e += 384) {
    const int u = e / kF, f = e - u * kF;
    asm volatile("st.shared.u32 [%0], %1;" ::"r"(sb + SP_IDX + e * 4), "r"(__ldg(idx + gsof(u) * kF + f)) : "memory");
  }
  build_coef(w_p, sb, tid);
  __syncthreads();
  const uint32_t ring = sb + warp * 2 * SP_BUF;
  const char* tb = reinterpret_cast<const char*>(table) + (lane & 15) * 16;
  const int hrow = lane >> 4;
  const uint32_t dpiece = ((lane & 15) ^ (hrow << 2)) * 16;
  auto fetch = [&](int u, int buf) {
    if (u < SP_N) {
      uint32_t r[13];
#pragma unroll
      for (int i = 0; i < 13; i++) asm volatile("ld.shared.u32 %0, [%1];" : "=r"(r[i]) : "r"(sb + SP_IDX + (u * kF + 2 * i + hrow) * 4));
#pragma unroll
      for (int i = 0; i < 13; i++) cp16(ring + buf * SP_BUF + (2 * i + hrow) * 256 + dpiece, tb + (size_t)(r[i] * 256u));
    }
    asm volatile("cp.async.commit_group;" ::: "memory");
  };
  fetch(warp, 0);
  fetch(warp + 12, 1);
  uint32_t z;
  asm volatile("ld.shared.u32 %0, [%1];" : "=r"(z) : "r"(sb + SP_IDX));
  z >>= 31;
  Coef cf;
  load_coef(cf, sb, lane);
  int buf = 0;
#pragma unroll 1
  for (int u = warp; u < SP_N; u += 12) {
    asm volatile("cp.async.wait_group 1;" ::: "memory");
    __syncwarp();
    Chunk ch[4];
    load_sample(ch, ring + buf * SP_BUF + g * 256 + q * 16, (g & 1) << 6, g < 2);
    float lp = gram_sample(ch, z, cf);
    __syncwarp();
    fetch(u + 24, buf);
    buf ^= 1;
#pragma unroll
    for (int o = 16; o > 0; o >>= 1) lp += __shfl_xor_sync(0xffffffffu, lp, o);
    if (lane == 0) asm volatile("st.relaxed.gpu.global.b64 [%0], %1;" ::"l"(&g_lp[gsof(u)]), "l"((1ull << 32) | __float_as_uint(lp)) : "memory");
  }
}

__global__ void __cluster_dims__(2, 1, 1) __launch_bounds__(384, 1)
fused_kernel(const __grid_constant__ CUtensorMap tmW1, const int* __restrict__ idx, const __nv_bfloat16* __restrict__ table,
             const __nv_bfloat16* __restrict__ w_p, const __nv_bfloat16* __restrict__ b1, const __nv_bfloat16* __restrict__ w2,
             const __nv_bfloat16* __restrict__ b2, __nv_bfloat16* __restrict__ out, int spare_first) {
  extern __shared__ __align__(1024) uint8_t smem[];
  const uint32_t sb = smem_u32(smem);
  const int tid = threadIdx.x, wg = tid >> 7, warp = tid >> 5, lane = tid & 31;
  const int cta = (int)blockIdx.x - spare_first;
  const int k = cta & 1, n = (cta >> 1) & 1, mt = cta >> 2;
  const uint32_t bar = sb + OFF_BAR;
  const int t7 = tid & 127;
  if (cta < 0 || cta >= 128) { pnn_spare(idx, table, w_p, sb, tid, cta < 0 ? cta + 4 : cta - 128); return; }

  if (wg < 2) {
    const __nv_bfloat16 b1v = b1[256 * n + tid], w2v = w2[256 * n + tid];
    asm volatile("bar.sync 1, 384;" ::: "memory");
    asm volatile("barrier.cluster.arrive.relaxed.aligned;" ::: "memory");
    if (tid == 128) {
#pragma unroll
      for (int i = 0; i < NST; i++) {
        mbar_expect_tx(bar + BAR_FULL + 8 * i, B_BYTES);
        tma3d(sb + i * STAGE + A_BYTES, &tmW1, 0, k * 1664 + i * 64, n * 4, bar + BAR_FULL + 8 * i);
        if (i == 0) {
          mbar_expect_tx(bar + BAR_IDX, 128 * kF * 4);
          asm volatile("cp.async.bulk.shared::cluster.global.mbarrier::complete_tx::bytes [%0], [%1], %2, [%3];"
                       ::"r"(sb + OFF_X), "l"(idx + mt * 128 * kF), "r"(128 * kF * 4), "r"(bar + BAR_IDX) : "memory");
        }
      }
#pragma unroll
      for (int i = 0; i < 4; i++) mbar_expect_tx(bar + BAR_XFULL + 8 * i, 8192);
      mbar_expect_tx(bar + BAR_XREADY, 16);
    }
    __syncwarp();
    asm volatile("st.shared.f32 [%0], %1;" ::"r"(sb + OFF_B1 + tid * 4), "f"(__bfloat162float(b1v)) : "memory");
    asm volatile("st.shared.f32 [%0], %1;" ::"r"(sb + OFF_W2 + tid * 4), "f"(0.5f * __bfloat162float(w2v)) : "memory");
    if (tid == 0) {
      asm volatile("st.shared.f32 [%0], %1;" ::"r"(sb + OFF_LP + 31 * 4), "f"(ldbf(b2, 0)) : "memory");
      asm volatile("st.shared.u32 [%0], %1;" ::"r"(sb + OFF_LP + 30 * 4), "r"(0) : "memory");
    }
    asm volatile("bar.sync 2, 256;" ::: "memory");
    asm volatile("barrier.cluster.wait.acquire.aligned;" ::: "memory");
    const bool keeper = (wg == k);
    const int q = lane & 3;
    float acc[128];
#pragma unroll
    for (int j = 0; j < 32; j++) {
      float bx, by;
      asm volatile("ld.shared.v2.f32 {%0,%1}, [%2];" : "=f"(bx), "=f"(by) : "r"(sb + OFF_B1 + q * 8 + j * 32));
      acc[4 * j + 0] = keeper ? bx : 0.f; acc[4 * j + 1] = keeper ? by : 0.f;
      acc[4 * j + 2] = keeper ? bx : 0.f; acc[4 * j + 3] = keeper ? by : 0.f;
    }
    const uint32_t a_off = wg * 8192;
    const uint64_t dA0 = make_desc(sb + a_off, 16, 1024), dB0 = make_desc(sb + A_BYTES, 8192, 1024);
    auto mma4 = [&](int s) {
      const uint64_t da = dA0 + (uint64_t)(s * (STAGE >> 4)), db = dB0 + (uint64_t)(s * (STAGE >> 4));
#pragma unroll
      for (int kk = 0; kk < 4; kk++) wgmma_n256(acc, da + kk * 2, db + kk * 128);
    };
    auto issue256 = [&](int s) {
      fence_async();
      wg_fence();
      mma4(s);
      wg_commit();
    };
#pragma unroll
    for (int i = 0; i < 128; i++) asm volatile("" : "+f"(acc[i]) :: "memory");
    mbar_wait(bar + BAR_FULL, 0);
    issue256(0);
#pragma unroll 1
    for (int it = 1; it < NITER - TAILN; it++) {
      const int s = it & 3;
      mbar_wait(bar + BAR_FULL + 8 * s, (it >> 2) & 1);
      issue256(s);
      wg_wait<1>();
      if (lane == 0) mbar_arrive(bar + BAR_EMPTY + 8 * ((it - 1) & 3));
    }
    float x[64];
    const uint32_t hb = sb + 1 * STAGE + t7 * 16;
    if (keeper) {
      wg_wait<0>();
      if (lane == 0) mbar_arrive(bar + BAR_EMPTY + 8 * 3);
      mbar_wait(bar + BAR_FULL + 8 * 0, 0);
      mbar_wait(bar + BAR_FULL + 8 * 1, 0);
      asm volatile("bar.sync 3, 256;" ::: "memory");
      fence_async();
      wg_fence();
      mma4(0); wg_commit();
      mma4(1); wg_commit();
      wg_wait<1>(); if (lane == 0) mbar_arrive(bar + BAR_EMPTY + 8 * 0);
      wg_wait<0>();
      if (lane == 0) { mbar_arrive(bar + BAR_EMPTY + 8 * 1); mbar_arrive(bar + BAR_GO); }
      asm volatile("bar.sync 7, 256;" ::: "memory");
#pragma unroll
      for (int i = 0; i < 16; i++)
        asm volatile("st.shared.v4.f32 [%0], {%1,%2,%3,%4};" ::"r"(hb + i * 2048), "f"(acc[64 + 4 * i]), "f"(acc[65 + 4 * i]), "f"(acc[66 + 4 * i]), "f"(acc[67 + 4 * i]) : "memory");
      asm volatile("bar.arrive 4, 256;" ::: "memory");
#pragma unroll
      for (int i = 0; i < 64; i++) asm volatile("mov.b32 %0, %1;" : "=f"(x[i]) : "f"(acc[i]));
    } else {
      mbar_wait(bar + BAR_FULL + 8 * 0, 0);
      issue256(0);
      wg_wait<1>(); if (lane == 0) mbar_arrive(bar + BAR_EMPTY + 8 * 3);
      mbar_wait(bar + BAR_FULL + 8 * 1, 0);
      issue256(1);
      asm volatile("bar.arrive 3, 256;" ::: "memory");
      wg_wait<1>(); if (lane == 0) mbar_arrive(bar + BAR_EMPTY + 8 * 0);
      mbar_wait(bar + BAR_XREADY, 0);
      const uint32_t rx = mapa(sb + OFF_X + t7 * 16, k ^ 1), rb = mapa(bar + BAR_XFULL, k ^ 1);
      wg_wait<0>();
      asm volatile("bar.arrive 7, 256;" ::: "memory");
      send_chunk<0>(acc, rx, rb); send_chunk<2>(acc, rx, rb); send_chunk<1>(acc, rx, rb); send_chunk<3>(acc, rx, rb);
    }
    const int half = keeper ? 0 : 1, cw = half * 4 + (warp & 3);
    const uint32_t zz = lds32(sb + OFF_LP + 30 * 4);
    if (!keeper) {
      asm volatile("bar.sync 4, 256;" ::: "memory");
#pragma unroll
      for (int i = 0; i < 16; i++)
        asm volatile("ld.shared.v4.f32 {%0,%1,%2,%3}, [%4];" : "=f"(x[4 * i]), "=f"(x[4 * i + 1]), "=f"(x[4 * i + 2]), "=f"(x[4 * i + 3]) : "r"(hb + i * 2048));
      uint32_t t = 0;
#pragma unroll
      for (int i = 0; i < 16; i++) asm volatile("or.b32 %0, %0, %1;" : "+r"(t) : "r"(__float_as_uint(x[4 * i])));
      t = __reduce_or_sync(0xffffffffu, t);
      if (lane == 0) mbar_arrive(bar + BAR_EMPTY + 8 * 1 + (t & zz));
      __syncwarp();
    }
    float lp[2] = {0.f, 0.f};
    const int p2 = cw < 3 ? 11 + cw : (cw < 6 ? 15 + cw : 19 + cw);
    if (cw < 7) lp[0] = pnn_one(sb, cw, lane, zz, false);
    const uint32_t xb = sb + OFF_X + half * 16384 + t7 * 16, w2a = sb + OFF_W2 + half * 512 + q * 8;
    float s0 = 0.f, s1 = 0.f;
    GeluOps o0, o1;
    mbar_wait(bar + BAR_XFULL + half * 16, 0);
    gelu_load(o0, xb, w2a);
    gelu_chunk<0>(x, o0, s0, s1);
    mbar_wait(bar + BAR_XFULL + half * 16 + 8, 0);
    gelu_load(o1, xb + 8192, w2a + 256);
    gelu_chunk<1>(x, o1, s0, s1);
    s0 += __shfl_xor_sync(0xffffffffu, s0, 1); s0 += __shfl_xor_sync(0xffffffffu, s0, 2);
    s1 += __shfl_xor_sync(0xffffffffu, s1, 1); s1 += __shfl_xor_sync(0xffffffffu, s1, 2);
    const int g = lane >> 2, r = 16 * (warp & 3) + g + 8 * (q & 1);
    float v = (q & 1) ? s1 : s0;
    const bool fin = keeper && ((warp & 3) >> 1) == n && q < 2;
    const int gs = mt * 128 + 64 * k + r;
    if (!keeper) {
      if (q < 2) asm volatile("st.shared.f32 [%0], %1;" ::"r"(sb + OFF_X + 16384 + (warp & 3) * 512 + (g + 8 * q) * 4), "f"(v) : "memory");
      asm volatile("bar.arrive 5, 256;" ::: "memory");
    } else {
      asm volatile("bar.sync 5, 256;" ::: "memory");
      if (q < 2) {
        v += __uint_as_float(lds32(sb + OFF_X + 16384 + (warp & 3) * 512 + (g + 8 * q) * 4));
        if (!fin) asm volatile("st.relaxed.gpu.global.b64 [%0], %1;" ::"l"(&g_slots[gs]), "l"((1ull << 32) | __float_as_uint(v)) : "memory");
      }
    }
    __syncwarp();
    unsigned long long o = 1ull, o2 = 1ull;
    const int pr_ = r & 31;
    if (fin && pr_ >= PNN_LOCAL) asm volatile("ld.relaxed.gpu.global.b64 %0, [%1];" : "=l"(o2) : "l"(&g_lp[gs]) : "memory");
    lp[1] = pnn_one(sb, p2, lane, zz, false);
    if (fin) asm volatile("ld.relaxed.gpu.global.b64 %0, [%1];" : "=l"(o) : "l"(&g_slots[gs]) : "memory");
    {
      const int pp[2] = {cw < 7 ? cw : -1, p2};
      pnn_publish(lp, pp, sb, lane);
    }
    if (fin) {
      int it = 0;
      float lpv;
      const float b2v = __uint_as_float(lds32(sb + OFF_LP + 31 * 4));
      if (pr_ >= PNN_LOCAL) {
        while (o2 == 0ull) { asm volatile("ld.relaxed.gpu.global.b64 %0, [%1];" : "=l"(o2) : "l"(&g_lp[gs]) : "memory"); if (++it > (1 << 20)) __trap(); }
        lpv = __uint_as_float((uint32_t)o2);
      } else {
        mbar_wait(bar + BAR_PNN, 0);
        lpv = __uint_as_float(lds32(sb + OFF_LP + pr_ * 4));
      }
      while (o == 0ull) { asm volatile("ld.relaxed.gpu.global.b64 %0, [%1];" : "=l"(o) : "l"(&g_slots[gs]) : "memory"); if (++it > (1 << 20)) __trap(); }
      out[gs] = __float2bfloat16(v + __uint_as_float((uint32_t)o) + lpv + b2v);
      asm volatile("st.relaxed.gpu.global.b64 [%0], %1;" ::"l"(&g_slots[gs]), "l"(0ull) : "memory");
      if (pr_ >= PNN_LOCAL) asm volatile("st.relaxed.gpu.global.b64 [%0], %1;" ::"l"(&g_lp[gs]), "l"(0ull) : "memory");
    }
  } else {
    const int w = warp - 8, c = lane & 7, rg = lane >> 3;
    const int r0 = w * 32 + rg * 8;
    uint32_t off[8];
    int id1[8];
    {
      const int* ip = idx + (mt * 128 + r0) * kF + 13 * k;
#pragma unroll
      for (int j = 0; j < 8; j++) { off[j] = __ldg(ip + j * kF); id1[j] = __ldg(ip + j * kF + 1); }
    }
    if (warp == 8) {
      if (lane == 0) {
        asm volatile("prefetch.tensormap [%0];" ::"l"(&tmW1) : "memory");
#pragma unroll
        for (int i = 0; i < NST; i++) { mbar_init(bar + BAR_FULL + 8 * i, 129); mbar_init(bar + BAR_EMPTY + 8 * i, 8); mbar_init(bar + BAR_XFULL + 8 * i, 1); }
        mbar_init(bar + BAR_XREADY, 1);
        mbar_init(bar + BAR_PNN, 12);
        mbar_init(bar + BAR_IDX, 1);
        mbar_init(bar + BAR_GO, 4);
        asm volatile("fence.mbarrier_init.release.cluster;" ::: "memory");
        fence_async();
      }
      __syncwarp();
    }
    asm volatile("bar.sync 1, 384;" ::: "memory");
    asm volatile("barrier.cluster.arrive.relaxed.aligned;" ::: "memory");
    const uint32_t dbase = sb + r0 * 128;
    const char* tb = reinterpret_cast<const char*>(table) + c * 16;
#pragma unroll
    for (int j = 0; j < 8; j++) off[j] *= 256u;
#pragma unroll
    for (int j = 0; j < 8; j++) cp16_256(dbase + 0 * STAGE + j * 128 + ((c ^ j) << 4), tb + off[j]);
    cp_arrive_noinc(bar + BAR_FULL + 0);
#pragma unroll
    for (int j = 0; j < 8; j++) cp16(dbase + 1 * STAGE + j * 128 + ((c ^ j) << 4), tb + off[j] + 128);
    cp_arrive_noinc(bar + BAR_FULL + 8);
#pragma unroll
    for (int j = 0; j < 8; j++) off[j] = (uint32_t)id1[j] * 256u;
#pragma unroll
    for (int j = 0; j < 8; j++) cp16_256(dbase + 2 * STAGE + j * 128 + ((c ^ j) << 4), tb + off[j]);
    cp_arrive_noinc(bar + BAR_FULL + 16);
#pragma unroll
    for (int j = 0; j < 8; j++) cp16(dbase + 3 * STAGE + j * 128 + ((c ^ j) << 4), tb + off[j] + 128);
    cp_arrive_noinc(bar + BAR_FULL + 24);
    build_coef(w_p, sb, t7);
    asm volatile("barrier.cluster.wait.acquire.aligned;" ::: "memory");
    mbar_wait(bar + BAR_IDX, 0);
    const int hr = t7 >> 4;
    uint32_t pr[89];
    {
      const uint32_t ia = sb + OFF_X + ((64 * k + 32 * n) * kF + hr) * 4;
#pragma unroll
      for (int v = 0; v < 3; v++) {
#pragma unroll
        for (int i = 0; i < 23; i++) {
          pr[v * 23 + i] = 0;
          if (i < 22 || hr < 6) asm volatile("ld.shared.u32 %0, [%1];" : "=r"(pr[v * 23 + i]) : "r"(ia + (v * 182 + 8 * i) * 4));
        }
      }
#pragma unroll
      for (int i = 0; i < 20; i++) {
        pr[69 + i] = 0;
        if (i < 19 || hr < 4) asm volatile("ld.shared.u32 %0, [%1];" : "=r"(pr[69 + i]) : "r"(ia + (546 + 8 * i) * 4));
      }
    }
    const uint32_t irow = sb + OFF_X + (r0 * kF + 13 * k) * 4;
    const char* tp = reinterpret_cast<const char*>(table) + (t7 & 15) * 16;
    const uint32_t doff = hr * 256 + (((t7 & 15) ^ ((hr & 1) << 2)) << 4);
    auto load_off = [&](uint32_t (&o)[8], int f) {
#pragma unroll
      for (int j = 0; j < 8; j++) { uint32_t v; asm volatile("ld.shared.u32 %0, [%1];" : "=r"(v) : "r"(irow + f * 4 + j * (kF * 4))); o[j] = v * 256u; }
    };
    auto produce = [&](int st, const uint32_t (&o)[8]) {
      const int s = st & 3;
      mbar_wait(bar + BAR_EMPTY + 8 * s, ((st >> 2) - 1) & 1);
      if (tid == 256) {
        mbar_expect_tx(bar + BAR_FULL + 8 * s, B_BYTES);
        tma3d(sb + s * STAGE + A_BYTES, &tmW1, 0, k * 1664 + st * 64, n * 4, bar + BAR_FULL + 8 * s);
      }
      __syncwarp();
      const uint32_t dst = dbase + s * STAGE;
      if ((st & 1) == 0) {
#pragma unroll
        for (int j = 0; j < 8; j++) cp16_256(dst + j * 128 + ((c ^ j) << 4), tb + o[j]);
      } else {
#pragma unroll
        for (int j = 0; j < 8; j++) cp16(dst + j * 128 + ((c ^ j) << 4), tb + o[j] + 128);
      }
      cp_arrive_noinc(bar + BAR_FULL + 8 * s);
    };
#pragma unroll 1
    for (int st = NST; st < 22; st++) {
      if ((st & 1) == 0) load_off(off, st >> 1);
      produce(st, off);
    }
    uint32_t off2[8];
    load_off(off, 11);
    load_off(off2, 12);
    asm volatile("bar.sync 6, 128;" ::: "memory");
    if (lane == 0)
      asm volatile("st.async.weak.shared::cluster.mbarrier::complete_tx::bytes.u32 [%0], %1, [%2];"
                   ::"r"(mapa(sb + OFF_LP + 28 * 4, k ^ 1)), "r"(0), "r"(mapa(bar + BAR_XREADY, k ^ 1)) : "memory");
    __syncwarp();
    produce(22, off);
    produce(23, off);
    produce(24, off2);
    produce(25, off2);
    auto stage_v = [&](int v, int cnt, int last) {
      const int s = (v + 2) & 3;
      mbar_wait(bar + BAR_EMPTY + 8 * s, (((26 + v) >> 2) - 1) & 1);
#pragma unroll
      for (int i = 0; i < 23; i++)
        if (i < cnt - 1 || (i == cnt - 1 && hr < last)) cp16(sb + s * STAGE + doff + i * 2048, tp + (size_t)(pr[v * 23 + i] * 256u));
      cp_arrive_noinc(bar + BAR_FULL + 8 * s);
      if (t7 == 0) mbar_arrive(bar + BAR_FULL + 8 * s);
      __syncwarp();
    };
    stage_v(0, 23, 6);
    stage_v(1, 23, 6);
    const uint32_t z = lds32(sb + OFF_LP + 30 * 4);
    float lp[3];
    lp[0] = pnn_one(sb, 7 + w, lane, z, true);
    stage_v(2, 23, 6);
    stage_v(3, 20, 4);
    lp[1] = pnn_one(sb, 14 + w, lane, z, false);
    lp[2] = pnn_one(sb, 21 + w, lane, z, false);
    const int pp[3] = {7 + w, 14 + w, 21 + w};
    pnn_publish(lp, pp, sb, lane);
  }
}

typedef CUresult (*PFN_encodeTiled)(CUtensorMap*, CUtensorMapDataType, cuuint32_t, void*, const cuuint64_t*, const cuuint64_t*, const cuuint32_t*,
                                    const cuuint32_t*, CUtensorMapInterleave, CUtensorMapSwizzle, CUtensorMapL2promotion, CUtensorMapFloatOOBfill);

}

extern "C" void kernel_launch(void* const* d_in, const int* in_sizes, int n_in, void* d_out, int out_size) {
  const int* idx = (const int*)d_in[0];
  const __nv_bfloat16* table = (const __nv_bfloat16*)d_in[1];
  const __nv_bfloat16* w_p = (const __nv_bfloat16*)d_in[2];
  const __nv_bfloat16* w1 = (const __nv_bfloat16*)d_in[3];
  const __nv_bfloat16* b1 = (const __nv_bfloat16*)d_in[4];
  const __nv_bfloat16* w2 = (const __nv_bfloat16*)d_in[5];
  const __nv_bfloat16* b2 = (const __nv_bfloat16*)d_in[6];
  static PFN_encodeTiled enc = nullptr;
  static int spare_first = 4;
  if (!enc) {
    void* fn = nullptr;
    cudaDriverEntryPointQueryResult st;
    cudaGetDriverEntryPoint("cuTensorMapEncodeTiled", &fn, cudaEnableDefault, &st);
    enc = (PFN_encodeTiled)fn;
    cudaFuncSetAttribute(fused_kernel, cudaFuncAttributeMaxDynamicSharedMemorySize, SMEM_BYTES);
    cudaLaunchConfig_t cfg = {};
    cfg.gridDim = dim3(132); cfg.blockDim = dim3(384); cfg.dynamicSmemBytes = SMEM_BYTES;
    cudaLaunchAttribute at[1];
    at[0].id = cudaLaunchAttributeClusterDimension; at[0].val.clusterDim.x = 2; at[0].val.clusterDim.y = 1; at[0].val.clusterDim.z = 1;
    cfg.attrs = at; cfg.numAttrs = 1;
    int nclusters = 0;
    if (cudaOccupancyMaxActiveClusters(&nclusters, fused_kernel, &cfg) != cudaSuccess) { nclusters = 0; (void)cudaGetLastError(); }
    spare_first = (nclusters >= 66) ? 0 : 4;
  }
  CUtensorMap tm;
  cuuint64_t dims[3] = {64, (cuuint64_t)(kF * kD), 8};
  cuuint64_t strides[2] = {(cuuint64_t)kH * 2, 128};
  cuuint32_t box[3] = {64, 64, 4};
  cuuint32_t es[3] = {1, 1, 1};
  enc(&tm, CU_TENSOR_MAP_DATA_TYPE_BFLOAT16, 3, (void*)w1, dims, strides, box, es, CU_TENSOR_MAP_INTERLEAVE_NONE,
      CU_TENSOR_MAP_SWIZZLE_128B, CU_TENSOR_MAP_L2_PROMOTION_L2_128B, CU_TENSOR_MAP_FLOAT_OOB_FILL_NONE);
  fused_kernel<<<132, 384, SMEM_BYTES, cudaStreamPerThread>>>(tm, idx, table, w_p, b1, w2, b2, (__nv_bfloat16*)d_out, spare_first);
}
```
